```python
import torch

def _softmax(x, axis=-1):
    return torch.softmax(x, dim=axis)

def _gelu(x):
    return torch.nn.functional.gelu(x, approximate='tanh')

def _silu(x):
    return torch.nn.functional.silu(x)

def _sigmoid(x):
    return torch.sigmoid(x)

def _layernorm(x, axis=-1, eps=1e-05):
    m = x.mean(dim=axis, keepdim=True)
    v = x.var(dim=axis, keepdim=True, unbiased=False)
    return (x - m) / torch.sqrt(v + eps)

def _scatter_add(tgt, idx, src, axis=0):
    return tgt.clone().index_add_(axis, idx, src)

def _segment_sum(src, seg, n):
    out = torch.zeros((n,) + src.shape[1:], dtype=src.dtype)
    return out.index_add_(0, seg, src)

def _pad(x, pw):
    flat = tuple((v for pair in reversed(pw) for v in pair))
    return torch.nn.functional.pad(x, flat)
kernel_name = 'adaLN_cond__sliding_block_cached__dense_activation_gelu__decode'

def setup_inputs():

    _w = lambda a: (lambda t: t.to(torch.bfloat16) if t.is_floating_point() else t)(torch.as_tensor(a))

    def _A_setup():
        B, Sq, D = (4, 1, 640)
        Hq, Hkv, Sk, Dh = (32, 32, 8192, 128)
        assert Hq % Hkv == 0, (Hq, Hkv)
        return {'x': _w((lambda *s: torch.randn(*s, dtype=torch.bfloat16) * 0.1)(B, Sq, D)), 'k_cache': _w((lambda *s: torch.randn(*s, dtype=torch.bfloat16) * 0.8)(B, Hkv, Sk, Dh)), 'v_cache': _w((lambda *s: torch.randn(*s, dtype=torch.bfloat16) * 3.2)(B, Hkv, Sk, Dh)), 'wq': _w((lambda *s: torch.randn(*s, dtype=torch.bfloat16) * 0.8)(D, Hq * Dh) * D ** (-0.5)), 'wo': _w((lambda *s: torch.randn(*s, dtype=torch.bfloat16) * 3.2)(Hq * Dh, D) * (Hq * Dh) ** (-0.5))}
    _A_in = _A_setup()

    def _B_setup():
        B, S, D, F = (4, 1, 640, 1728)
        return {'x': _w((lambda *s: torch.randn(*s, dtype=torch.bfloat16) * 0.1)(B, S, D)), 'w1': _w((lambda *s: torch.randn(*s, dtype=torch.bfloat16) * 3.2)(D, F) * D ** (-0.5)), 'b1': _w((lambda *s: torch.randn(*s, dtype=torch.bfloat16) * 3.2)(F) * 0.01), 'w2': _w((lambda *s: torch.randn(*s, dtype=torch.bfloat16) * 3.2)(F, D) * F ** (-0.5)), 'b2': _w((lambda *s: torch.randn(*s, dtype=torch.bfloat16) * 3.2)(D) * 0.01)}
    _B_in = _B_setup()
    return {'A_x': _A_in['x'], 'A_k_cache': _A_in['k_cache'], 'A_v_cache': _A_in['v_cache'], 'A_wq': _A_in['wq'], 'A_wo': _A_in['wo'], 'B_x': _B_in['x'], 'B_w1': _B_in['w1'], 'B_b1': _B_in['b1'], 'B_w2': _B_in['w2'], 'B_b2': _B_in['b2'], 'c': _w((lambda *s: torch.randn(*s, dtype=torch.bfloat16) * 0.1)(4, 640) * 8.0), 'w_mod': _w((lambda *s: torch.randn(*s, dtype=torch.bfloat16) * 0.1)(640, 6 * 640) * 640 ** (-0.5) * 8.0)}

def reference(A_x, A_k_cache, A_v_cache, A_wq, A_wo, B_x, B_w1, B_b1, B_w2, B_b2, c, w_mod):

    def _A_ref(x, k_cache, v_cache, wq, wo):
        B, Sq, D = x.shape
        Hq, Dh = (32, 128)
        Hkv, Sk = (k_cache.shape[1], k_cache.shape[2])
        W = min(4096, max(256, Sk // 4))
        rep = Hq // Hkv
        q = (lambda x, *d: x.permute(*d))((x @ wq).reshape(B, Sq, Hq, Dh), 0, 2, 1, 3)
        k = (lambda x, n, axis: torch.repeat_interleave(x, n, dim=axis))(k_cache[:, :, Sk - W:, :], rep, axis=1)
        v = (lambda x, n, axis: torch.repeat_interleave(x, n, dim=axis))(v_cache[:, :, Sk - W:, :], rep, axis=1)
        scores = torch.einsum('bhqd,bhkd->bhqk', q, k) * Dh ** (-0.5)
        p = _softmax(scores, axis=-1)
        o = torch.einsum('bhqk,bhkd->bhqd', p, v)
        return (lambda x, *d: x.permute(*d))(o, 0, 2, 1, 3).reshape(B, Sq, Hq * Dh) @ wo

    def _B_ref(x, w1, b1, w2, b2):
        h = torch.einsum('bsd,df->bsf', x, w1) + b1
        h = _gelu(h)
        return torch.einsum('bsf,fd->bsd', h, w2) + b2
    x = A_x
    mod = (_silu(c) @ w_mod).reshape(c.shape[0], 6, 1, -1)
    sa, ca, ga, sb, cb, gb = (mod[:, 0].clone(), mod[:, 1].clone(), mod[:, 2].clone(), mod[:, 3].clone(), mod[:, 4].clone(), mod[:, 5].clone())
    h = _layernorm(x, axis=-1) * (1 + ca) + sa
    x = x + ga * _A_ref(h, A_k_cache, A_v_cache, A_wq, A_wo)
    h = _layernorm(x, axis=-1) * (1 + cb) + sb
    x = x + gb * _B_ref(h, B_w1, B_b1, B_w2, B_b2)
    return x
```

```cpp
#include <cuda_runtime.h>
#include <cuda_bf16.h>
#include <cuda.h>
#include <stdint.h>

namespace {

constexpr int DM = 640, NH = 32, DH = 128, SK = 8192, WIN = 2048, FF = 1728;
constexpr int NCTA = 128;
constexpr int NGW = 10;
constexpr int NAW = 4;
constexpr int NTHR = (NGW + 1 + NAW) * 32;
constexpr int TILE_KEYS = 32;
constexpr int TILE_BYTES = TILE_KEYS * DH * 2;
constexpr int NSLOT = 24;
constexpr int KT = WIN / NAW / TILE_KEYS;
constexpr int IT_MOD = 0, IT_WQ = 5, IT_K = 10, IT_V = IT_K + NAW * KT, IT_WO = IT_V + NAW * KT, IT_FF = IT_WO + 5;
constexpr int MID_LO = 23, CNT_LO = 8, CNT_HI = 128;
constexpr int W_PRO = 5;
constexpr int W_MID = 182;
constexpr int MID_HI = 128;
constexpr int VE_D = 40;
constexpr int VE_S = 34;
constexpr int WO_D = 23;
constexpr int WO_S = 44;
constexpr int F1_D = 58;
constexpr int F1_S = 15;
constexpr int F2_D = 146;
constexpr int F2_S = 13;
constexpr int F3_D = 79;
constexpr int F3_S = 16;
constexpr int CLK32 = 18;
constexpr int PHASE = 32;
constexpr int SMP_NS = 300;
constexpr int INIT_NS = 6000;
constexpr int MOD_CLK = 1200;
constexpr int Q_CLK = 900;
constexpr int NPROBE = 3;
constexpr int NPROBE_MAX = 12;
constexpr int NPF = 2;
constexpr int N_MOD_CTA = 100;
constexpr int N_W1_CTA = 54;
constexpr unsigned SPIN_MAX = 1u << 20;

constexpr int SM_RING = 0;
constexpr int SM_SCORE = SM_RING + NSLOT * TILE_BYTES;
constexpr int SM_RED1 = SM_SCORE, SM_RED2 = SM_SCORE + 5 * 512;
constexpr int SM_P = SM_SCORE + NAW * 512 * 4;
constexpr int ACT_LD = DM * 2 + 16, OACT_LD = 2 * DH * 2 + 16;
constexpr int SM_ACT = SM_P + NAW * 512 * 2;
constexpr int SM_PRE = SM_ACT + 4 * ACT_LD;
constexpr int SM_OACT = SM_PRE + 8 * ACT_LD;
constexpr int SM_RED = SM_OACT + 4 * OACT_LD;
constexpr int SM_ORED = SM_RED2 + 5 * 512;
constexpr int SM_ML = SM_RED + 7 * 512;
constexpr int SM_ST = SM_ML + 32;
constexpr int SM_PIV = SM_ST + 32;
constexpr int NSEG = 8;
constexpr int SM_SEG = SM_PIV + 16;
constexpr int SM_TREF = SM_SEG + NSEG * 32;
constexpr int SM_FULL = SM_TREF + 16;
constexpr int SM_EMPTY = SM_FULL + 8 * NSLOT;
constexpr int SM_BML = SM_EMPTY + 8 * NSLOT;
constexpr int SM_BTRIG = SM_BML + 8;
constexpr int SM_BSEG = SM_BTRIG + 8;
constexpr int SM_BATOM = SM_BSEG + 8;
constexpr int SM_BPRE = SM_BSEG + 16;
constexpr int SM_TOTAL = SM_BSEG + 64;
static_assert(NSLOT == 24 && NTHR == 480, "barrier initialisation");
static_assert(SM_TOTAL <= 232448, "shared memory");
static_assert(CNT_HI > IT_FF + 7 - NSLOT, "tail barriers");
static_assert(MID_LO < NSLOT, "window mode does not check for free slots");
static_assert(IT_WO % NSLOT + 5 <= NSLOT, "the wo slab needs five contiguous slots");
constexpr int WO_BYTES = 64 * 80 * 2;

constexpr int BAR_INIT = 0;
constexpr int BAR_INIT2 = 7;
constexpr int BAR_ACT = 1;
constexpr int BAR_RED = 2;
constexpr int BAR_A = 3;
constexpr int BAR_ACT2 = 4;
constexpr int BAR_RED2 = 5;
constexpr int N_AG5 = (NAW + 5) * 32, N_AG7 = (NAW + 7) * 32;

constexpr int HALF = 1024;
struct __align__(524288) Scratch {
    uint32_t o[8][2 * HALF];
    uint32_t x2[4][2 * HALF];
    uint32_t h1[4][2 * HALF];
    uint32_t gb[2][2 * HALF];
    uint32_t probe[4][2 * HALF];
    float4 acc[40][32];
    uint32_t init_cnt;
    uint32_t prog;
    uint32_t pad[30];
    uint32_t mod[4][1920];
    uint32_t q[4][2048];
};
__device__ Scratch g_s;
__device__ __forceinline__ uint32_t* o_at(int hp, int b) { return &g_s.o[hp >> 1][(hp & 1) * 512 + b * 128]; }
__device__ __forceinline__ uint32_t* x2_at(int b, int w) { return &g_s.x2[b][(w & 127) + (w >> 7) * 256]; }
__device__ __forceinline__ uint32_t* h1_at(int blk) { return &g_s.h1[blk >> 4][(blk & 15) * 64]; }
__device__ __forceinline__ uint32_t* gb_at(int b) { return &g_s.gb[b >> 1][(b & 1) * 320]; }
__device__ __forceinline__ uint32_t block_parity(const void* p) {
    const uint32_t b = (uint32_t)((const char*)p - (const char*)&g_s) >> 13;
    return (b ^ (b >> 3) ^ (b >> 4)) & 1;
}
__device__ __forceinline__ const uint32_t* near_copy(const uint32_t* p, uint32_t side) { return p + (side ^ block_parity(p)) * HALF; }
constexpr uint32_t NONE = 0xffffffffu;

__device__ __forceinline__ void mbar_init(uint32_t a, uint32_t c) {
    asm volatile("mbarrier.init.shared::cta.b64 [%0], %1;" ::"r"(a), "r"(c) : "memory");
}
__device__ __forceinline__ void mbar_expect(uint32_t a, uint32_t bytes) {
    asm volatile("mbarrier.arrive.expect_tx.shared::cta.b64 _, [%0], %1;" ::"r"(a), "r"(bytes) : "memory");
}
__device__ __forceinline__ void mbar_arrive(uint32_t a) {
    asm volatile("mbarrier.arrive.shared::cta.b64 _, [%0];" ::"r"(a) : "memory");
}
__device__ __forceinline__ void mbar_arrive_n(uint32_t a, uint32_t n) {
    asm volatile("mbarrier.arrive.shared::cta.b64 _, [%0], %1;" ::"r"(a), "r"(n) : "memory");
}
__device__ __forceinline__ void mbar_wait(uint32_t a, uint32_t parity) {
    asm volatile("{\n.reg .pred p, q;\n.reg .u32 n;\n"
                 "mbarrier.try_wait.parity.shared::cta.b64 p, [%0], %1;\n"
                 "@p bra.uni DONE;\n"
                 "mov.u32 n, 0;\n"
                 "LOOP:\n.pragma \"nounroll\";\n"
                 "mbarrier.try_wait.parity.shared::cta.b64 p, [%0], %1;\n"
                 "@p bra.uni DONE;\n"
                 "add.u32 n, n, 1;\n"
                 "setp.lt.u32 q, n, %2;\n"
                 "@q bra.uni LOOP;\n"
                 "DONE:\n}" ::"r"(a), "r"(parity), "n"(SPIN_MAX) : "memory");
}
template <int NS>
__device__ __forceinline__ void mbar_wait_sleep(uint32_t a) {
    asm volatile("{\n.reg .pred p;\n.reg .u32 n;\nmov.u32 n, 0;\nLOOP:\n.pragma \"nounroll\";\n"
                 "mbarrier.test_wait.parity.shared::cta.b64 p, [%0], 0;\n@p bra.uni DONE;\nnanosleep.u32 %1;\n"
                 "add.u32 n, n, 1;\nsetp.lt.u32 p, n, 0x100000;\n@p bra.uni LOOP;\nDONE:\n}" ::"r"(a), "n"(NS) : "memory");
}
__device__ __forceinline__ uint32_t lds32v(uint32_t a) {
    uint32_t v;
    asm volatile("ld.volatile.shared.u32 %0, [%1];" : "=r"(v) : "r"(a) : "memory");
    return v;
}
__device__ __forceinline__ uint32_t sm_clock() {
    uint32_t c;
    asm volatile("mov.u32 %0, %%clock;" : "=r"(c));
    return c;
}
__device__ __forceinline__ uint32_t sm_clock_after(uint32_t dep) {
    uint32_t c;
    asm volatile("{\n.reg .pred p;\nsetp.ge.s32 p, %1, 0;\nmov.u32 %0, 0;\n@p mov.u32 %0, %%clock;\n}" : "=r"(c) : "r"(dep));
    return c;
}
__device__ __forceinline__ uint64_t stream_policy() {
    uint64_t pol;
    asm("createpolicy.fractional.L2::evict_first.b64 %0, 1.0;" : "=l"(pol));
    return pol;
}
__device__ __forceinline__ void tma2d(uint32_t dst, const CUtensorMap* map, int c0, int c1, uint32_t mb) {
    asm volatile("cp.async.bulk.tensor.2d.shared::cluster.global.mbarrier::complete_tx::bytes.L2::cache_hint [%0], [%1, {%2, %3}], [%4], %5;"
                 ::"r"(dst), "l"(map), "r"(c0), "r"(c1), "r"(mb), "l"(stream_policy()) : "memory");
}
__device__ __forceinline__ bool elect_one() {
    uint32_t e;
    asm volatile("{\n.reg .pred p;\nelect.sync _|p, 0xffffffff;\nselp.u32 %0, 1, 0, p;\n}" : "=r"(e));
    return e;
}
template <class T> __device__ __forceinline__ void pin(T*& v) { asm volatile("" : "+l"(v)); }
__device__ __forceinline__ void pin(uint32_t& v) { asm volatile("" : "+r"(v)); }
__device__ __forceinline__ void bar_sync(int id, int n) { asm volatile("bar.sync %0, %1;" ::"r"(id), "r"(n) : "memory"); }
__device__ __forceinline__ void bar_arrive(int id, int n) { asm volatile("bar.arrive %0, %1;" ::"r"(id), "r"(n) : "memory"); }

__device__ __forceinline__ void mma16816(float (&c)[4], uint32_t a0, uint32_t a1, uint32_t a2, uint32_t a3,
                                         uint32_t b0, uint32_t b1) {
    asm volatile("mma.sync.aligned.m16n8k16.row.col.f32.bf16.bf16.f32 {%0,%1,%2,%3}, {%4,%5,%6,%7}, {%8,%9}, {%0,%1,%2,%3};"
                 : "+f"(c[0]), "+f"(c[1]), "+f"(c[2]), "+f"(c[3])
                 : "r"(a0), "r"(a1), "r"(a2), "r"(a3), "r"(b0), "r"(b1));
}
__device__ __forceinline__ void ldsm4t(uint32_t* r, uint32_t a) {
    asm volatile("ldmatrix.sync.aligned.m8n8.x4.trans.shared.b16 {%0,%1,%2,%3}, [%4];"
                 : "=r"(r[0]), "=r"(r[1]), "=r"(r[2]), "=r"(r[3]) : "r"(a) : "memory");
}
__device__ __forceinline__ void ldsm4(uint32_t* r, uint32_t a) {
    asm volatile("ldmatrix.sync.aligned.m8n8.x4.shared.b16 {%0,%1,%2,%3}, [%4];"
                 : "=r"(r[0]), "=r"(r[1]), "=r"(r[2]), "=r"(r[3]) : "r"(a) : "memory");
}
__device__ __forceinline__ uint4 lds128(uint32_t a) {
    uint4 v;
    asm volatile("ld.shared.v4.u32 {%0,%1,%2,%3}, [%4];" : "=r"(v.x), "=r"(v.y), "=r"(v.z), "=r"(v.w) : "r"(a) : "memory");
    return v;
}
__device__ __forceinline__ float2 lds64f(uint32_t a) {
    float2 v;
    asm volatile("ld.shared.v2.f32 {%0,%1}, [%2];" : "=f"(v.x), "=f"(v.y) : "r"(a) : "memory");
    return v;
}
__device__ __forceinline__ float lds32f(uint32_t a) {
    float v;
    asm volatile("ld.shared.f32 %0, [%1];" : "=f"(v) : "r"(a) : "memory");
    return v;
}
__device__ __forceinline__ void sts128f(uint32_t a, float x, float y, float z, float w) {
    asm volatile("st.shared.v4.f32 [%0], {%1,%2,%3,%4};" ::"r"(a), "f"(x), "f"(y), "f"(z), "f"(w) : "memory");
}
__device__ __forceinline__ void sts64(uint32_t a, uint32_t x, uint32_t y) {
    asm volatile("st.shared.v2.u32 [%0], {%1,%2};" ::"r"(a), "r"(x), "r"(y) : "memory");
}
__device__ __forceinline__ void sts32(uint32_t a, uint32_t x) {
    asm volatile("st.shared.u32 [%0], %1;" ::"r"(a), "r"(x) : "memory");
}
__device__ __forceinline__ void sts32f(uint32_t a, float x) { sts32(a, __float_as_uint(x)); }
__device__ __forceinline__ void sts16(uint32_t a, uint32_t x) {
    asm volatile("st.shared.u16 [%0], %1;" ::"r"(a), "h"((unsigned short)x) : "memory");
}
__device__ __forceinline__ uint32_t ldw16(const void* p) {
    uint32_t v;
    asm volatile("ld.global.nc.L1::no_allocate.u16 %0, [%1];" : "=r"(v) : "l"(p));
    return v;
}
__device__ __forceinline__ uint2 ldx64(const void* p) {
    uint2 v;
    asm volatile("ld.relaxed.gpu.global.v2.u32 {%0,%1}, [%2];" : "=r"(v.x), "=r"(v.y) : "l"(p) : "memory");
    return v;
}
__device__ __forceinline__ void ldx64_if(uint2& v, const void* p, bool c) {
    asm volatile("{\n.reg .pred p;\nsetp.ne.u32 p, %3, 0;\n@p ld.relaxed.gpu.global.v2.u32 {%0,%1}, [%2];\n}"
                 : "+r"(v.x), "+r"(v.y) : "l"(p), "r"((uint32_t)c) : "memory");
}
__device__ __forceinline__ uint32_t ldx32(const void* p) {
    uint32_t v;
    asm volatile("ld.relaxed.gpu.global.u32 %0, [%1];" : "=r"(v) : "l"(p) : "memory");
    return v;
}
__device__ __forceinline__ void stx32(void* p, uint32_t v) {
    asm volatile("st.relaxed.gpu.global.u32 [%0], %1;" ::"l"(p), "r"(v) : "memory");
}
__device__ __forceinline__ void stx128(void* p, uint32_t v) {
    asm volatile("st.relaxed.gpu.global.v4.u32 [%0], {%1,%1,%1,%1};" ::"l"(p), "r"(v) : "memory");
}
__device__ __forceinline__ void publish(const void* p, uint32_t v) {
    asm volatile("red.relaxed.gpu.global.and.b32 [%0], %1;" ::"l"(p), "r"(v) : "memory");
}
__device__ __forceinline__ void store_out_if(void* p, uint32_t v, bool c, bool done) {
    asm volatile("{\n.reg .pred p, q;\nsetp.ne.u32 p, %2, 0;\nsetp.ne.u32 q, %3, 0;\n@p st.global.u16 [%0], %1;\n"
                 "@q exit;\n"
                 "}" ::"l"(p), "h"((unsigned short)v), "r"((uint32_t)c), "r"((uint32_t)done) : "memory");
}
__device__ __forceinline__ float4 atom128(void* p, float x, float y, float z) {
    float4 r;
    asm volatile("atom.relaxed.gpu.global.add.v4.f32 {%0,%1,%2,%3}, [%4], {%5,%6,%7,%8};"
                 : "=f"(r.x), "=f"(r.y), "=f"(r.z), "=f"(r.w) : "l"(p), "f"(x), "f"(y), "f"(z), "f"(0.f) : "memory");
    return r;
}
__device__ __forceinline__ uint32_t pack2(float lo, float hi) {
    uint32_t r;
    asm("cvt.rn.bf16x2.f32 %0, %1, %2;" : "=r"(r) : "f"(hi), "f"(lo));
    return r;
}
__device__ __forceinline__ float blo(uint32_t w) { return __uint_as_float(w << 16); }
__device__ __forceinline__ float bhi(uint32_t w) { return __uint_as_float(w & 0xffff0000u); }
__device__ __forceinline__ float ex2(float v) {
    float r;
    asm("ex2.approx.ftz.f32 %0, %1;" : "=f"(r) : "f"(v));
    return r;
}
__device__ __forceinline__ float rcp(float v) {
    float r;
    asm("rcp.approx.ftz.f32 %0, %1;" : "=f"(r) : "f"(v));
    return r;
}
__device__ __forceinline__ uint32_t mul2(uint32_t a, uint32_t b) {
    uint32_t r;
    asm("mul.rn.bf16x2 %0, %1, %2;" : "=r"(r) : "r"(a), "r"(b));
    return r;
}
__device__ __forceinline__ uint32_t add2(uint32_t a, uint32_t b) {
    uint32_t r;
    asm("add.rn.bf16x2 %0, %1, %2;" : "=r"(r) : "r"(a), "r"(b));
    return r;
}
__device__ __forceinline__ float sum5(uint32_t a) {
    return ((lds32f(a) + lds32f(a + 512)) + (lds32f(a + 1024) + lds32f(a + 1536))) + lds32f(a + 2048);
}
constexpr float LOG2E = 1.4426950408889634f;
__device__ __forceinline__ float mul_sigmoid2(float v, float z) { return v * rcp(1.f + ex2(-z)); }

#define POLL_TAIL(SLEEP) \
    ".reg .pred more;\nadd.u32 n, n, 1;\nsetp.lt.u32 more, n, 0x100000;\n" \
    "vote.sync.any.pred q, q, 0xffffffff;\n@!q bra.uni DONE;\n" SLEEP "@more bra.uni LOOP;\nDONE:\n}"
__device__ __forceinline__ void pause_until(uint32_t due) {
    asm volatile("{\n.reg .pred q;\n.reg .u32 n, m;\nmov.u32 n, 0;\nLOOP:\n.pragma \"nounroll\";\n"
                 "mov.u32 m, %%clock;\nsub.u32 m, %0, m;\nsetp.gt.s32 q, m, 0;\n" POLL_TAIL("nanosleep.u32 40;\n") ::"r"(due) : "memory");
}
template <int NS>
__device__ __forceinline__ uint32_t poll32(const uint32_t* p, uint32_t bad) {
    uint32_t v;
    asm volatile("{\n.reg .pred q;\n.reg .u32 n;\nmov.u32 n, 0;\nLOOP:\n.pragma \"nounroll\";\n"
                 "ld.relaxed.gpu.global.u32 %0, [%1];\nsetp.eq.u32 q, %0, %2;\n"
                 POLL_TAIL("nanosleep.u32 %3;\n") : "=&r"(v) : "l"(p), "r"(bad), "n"(NS) : "memory");
    return v;
}
__device__ __forceinline__ uint4 poll128(const uint32_t* p) {
    uint4 v;
    asm volatile("{\n.reg .pred q, a;\n.reg .u32 n, m;\nmov.u32 n, 0;\nsetp.eq.u32 a, n, 0;\nLOOP:\n.pragma \"nounroll\";\n"
                 "@a ld.relaxed.gpu.global.v4.u32 {%0,%1,%2,%3}, [%4];\n"
                 "max.u32 m, %0, %1;\nmax.u32 m, m, %2;\nmax.u32 m, m, %3;\nsetp.eq.u32 a, m, 0xffffffff;\nmov.pred q, a;\n"
                 POLL_TAIL("") : "=&r"(v.x), "=&r"(v.y), "=&r"(v.z), "=&r"(v.w) : "l"(p) : "memory");
    return v;
}
#define X2_PIECE(A, B, C, D, OFF) "mul.rn.bf16x2 y, " A ", " C ";\nmul.rn.bf16x2 z, " B ", " D ";\nst.shared.v2.b32 [%22+" OFF "], {y, z};\n"
__device__ __forceinline__ void poll_x2(uint2 (&v)[5], const uint32_t* p, uint32_t gate, const float2 (&sc)[5], uint32_t dst) {
    asm volatile("{\n.reg .pred q, more, a<5>;\n.reg .u32 n, m, k, m<5>;\n.reg .b32 y, z;\nmov.u32 n, 0x200000;\n"
                 "setp.ne.u32 a0, n, 0;\nmov.pred a1, a0;\nmov.pred a2, a0;\nmov.pred a3, a0;\nmov.pred a4, a0;\nLOOP:\n.pragma \"nounroll\";\n"
                 "@a0 ld.relaxed.gpu.global.v2.u32 {%0,%1}, [%10];\n@a1 ld.relaxed.gpu.global.v2.u32 {%2,%3}, [%10+256];\n"
                 "@a2 ld.relaxed.gpu.global.v2.u32 {%4,%5}, [%10+1024];\n@a3 ld.relaxed.gpu.global.v2.u32 {%6,%7}, [%10+1280];\n"
                 "@a4 ld.relaxed.gpu.global.v2.u32 {%8,%9}, [%10+2048];\n"
                 X2_PIECE("%0", "%1", "%12", "%13", "0") X2_PIECE("%2", "%3", "%14", "%15", "256") X2_PIECE("%4", "%5", "%16", "%17", "512")
                 X2_PIECE("%6", "%7", "%18", "%19", "768") X2_PIECE("%8", "%9", "%20", "%21", "1024")
                 "max.u32 m0, %0, %1;\nmax.u32 m1, %2, %3;\nmax.u32 m2, %4, %5;\nmax.u32 m3, %6, %7;\nmax.u32 m4, %8, %9;\n"
                 "max.u32 m, m0, m1;\nmax.u32 m, m, m2;\nmax.u32 m, m, m3;\nmax.u32 m, m, m4;\nsetp.eq.u32 q, m, 0xffffffff;\n"
                 "setp.eq.u32 a0, m0, 0xffffffff;\nsetp.eq.u32 a1, m1, 0xffffffff;\nsetp.eq.u32 a2, m2, 0xffffffff;\n"
                 "setp.eq.u32 a3, m3, 0xffffffff;\nsetp.eq.u32 a4, m4, 0xffffffff;\n"
                 "add.u32 n, n, 1;\nsetp.lt.u32 more, n, 0x100000;\nvote.sync.any.pred q, q, 0xffffffff;\n@!q bra.uni DONE;\n@more bra.uni LOOP;\n"
                 "setp.eq.u32 q, n, 0x100000;\n@q bra.uni DONE;\nmov.u32 n, 0;\nGATE:\n.pragma \"nounroll\";\n"
                 "mbarrier.try_wait.parity.shared::cta.b64 q, [%11], 0;\n@q bra.uni LOOP;\n"
                 "add.u32 n, n, 1;\nsetp.lt.u32 q, n, 0x80000;\n@q bra.uni GATE;\nbra.uni LOOP;\nDONE:\n}"
                 : "=&r"(v[0].x), "=&r"(v[0].y), "=&r"(v[1].x), "=&r"(v[1].y), "=&r"(v[2].x), "=&r"(v[2].y),
                   "=&r"(v[3].x), "=&r"(v[3].y), "=&r"(v[4].x), "=&r"(v[4].y)
                 : "l"(p), "r"(gate), "r"(__float_as_uint(sc[0].x)), "r"(__float_as_uint(sc[0].y)), "r"(__float_as_uint(sc[1].x)),
                   "r"(__float_as_uint(sc[1].y)), "r"(__float_as_uint(sc[2].x)), "r"(__float_as_uint(sc[2].y)), "r"(__float_as_uint(sc[3].x)),
                   "r"(__float_as_uint(sc[3].y)), "r"(__float_as_uint(sc[4].x)), "r"(__float_as_uint(sc[4].y)), "r"(dst) : "memory");
}
#define PIECE_CHECK(OP, BAD, P, A, B, C, D) OP " m, " A ", " B ";\n" OP " m, m, " C ";\n" OP " m, m, " D ";\nsetp.eq.u32 " P ", m, " BAD ";\n"
#define POLL4(OP, BAD, SLEEP) \
    "{\n.reg .pred q, a, b, c, d;\n.reg .u32 n, m;\nmov.u32 n, 0;\nbra.uni CHECK;\nLOOP:\n.pragma \"nounroll\";\n" \
    "@a ld.relaxed.gpu.global.v4.u32 {%0,%1,%2,%3}, [%16];\n@b ld.relaxed.gpu.global.v4.u32 {%4,%5,%6,%7}, [%17];\n" \
    "@c ld.relaxed.gpu.global.v4.u32 {%8,%9,%10,%11}, [%16+%18];\n@d ld.relaxed.gpu.global.v4.u32 {%12,%13,%14,%15}, [%17+%18];\n" \
    "CHECK:\n" PIECE_CHECK(OP, BAD, "a", "%0", "%1", "%2", "%3") PIECE_CHECK(OP, BAD, "b", "%4", "%5", "%6", "%7") \
    PIECE_CHECK(OP, BAD, "c", "%8", "%9", "%10", "%11") PIECE_CHECK(OP, BAD, "d", "%12", "%13", "%14", "%15") \
    "or.pred q, a, b;\nor.pred q, q, c;\nor.pred q, q, d;\n" POLL_TAIL(SLEEP)
#define POLL4_REGS(v) "+r"(v[0]), "+r"(v[1]), "+r"(v[2]), "+r"(v[3]), "+r"(v[4]), "+r"(v[5]), "+r"(v[6]), "+r"(v[7]), \
                      "+r"(v[8]), "+r"(v[9]), "+r"(v[10]), "+r"(v[11]), "+r"(v[12]), "+r"(v[13]), "+r"(v[14]), "+r"(v[15])
__device__ __forceinline__ void poll_h1(uint32_t (&v)[16], const uint32_t* p) {
    asm volatile(POLL4("max.u32", "0xffffffff", "") : POLL4_REGS(v) : "l"(p), "l"(p + 128), "n"(1024) : "memory");
}
__device__ __forceinline__ void poll_q(uint32_t (&v)[16], const uint32_t* p0, const uint32_t* p1) {
    asm volatile(POLL4("min.u32", "0", "nanosleep.u32 64;\n") : POLL4_REGS(v) : "l"(p0), "l"(p1), "n"(128) : "memory");
}
#define ROW_PIECE(A, B, OFF) "min.u32 m, " A ", " B ";\nsetp.eq.u32 a, m, 0;\n@a ld.relaxed.gpu.global.v2.u32 {" A "," B "}, [%10+" OFF "];\nor.pred q, q, a;\n"
__device__ __forceinline__ void poll_row(uint2* v, const uint32_t* p) {
    asm volatile("{\n.reg .pred q, a;\n.reg .u32 n, m;\nmov.u32 n, 0;\nLOOP:\n.pragma \"nounroll\";\nsetp.ne.u32 q, n, n;\n"
                 ROW_PIECE("%0", "%1", "0") ROW_PIECE("%2", "%3", "256") ROW_PIECE("%4", "%5", "512")
                 ROW_PIECE("%6", "%7", "768") ROW_PIECE("%8", "%9", "1024") POLL_TAIL("")
                 : "+r"(v[0].x), "+r"(v[0].y), "+r"(v[1].x), "+r"(v[1].y), "+r"(v[2].x), "+r"(v[2].y),
                   "+r"(v[3].x), "+r"(v[3].y), "+r"(v[4].x), "+r"(v[4].y) : "l"(p) : "memory");
}
__device__ __forceinline__ void poll_shift_scale(uint2 (&r)[10], const uint32_t* row, uint32_t pre_row) {
#pragma unroll
    for (int i = 5; i < 10; i++) ldx64_if(r[i], row + 64 * i, min(r[i].x, r[i].y) == 0);
    poll_row(&r[0], row);
    poll_row(&r[5], row + 320);
#pragma unroll
    for (int i = 0; i < 5; i++) {
        sts64(pre_row + i * 256, add2(~r[5 + i].x, 0x3f803f80u), add2(~r[5 + i].y, 0x3f803f80u));
        sts64(pre_row + 4 * ACT_LD + i * 256, ~r[i].x, ~r[i].y);
    }
}

__device__ __forceinline__ void load_a(uint32_t (&w)[64], uint32_t a0, bool narrow) {
    const uint32_t a1 = narrow ? a0 + 1024 : a0 ^ 32, a2 = a0 + (narrow ? 512 : 1024), a3 = a1 + (narrow ? 512 : 1024);
#pragma unroll
    for (int j = 0; j < 4; j++) {
        ldsm4t(&w[16 * j], a0 + j * 2048); ldsm4t(&w[16 * j + 4], a1 + j * 2048);
        ldsm4t(&w[16 * j + 8], a2 + j * 2048); ldsm4t(&w[16 * j + 12], a3 + j * 2048);
    }
}
__device__ __forceinline__ void gemv_mma(float (&c)[4][4], const uint32_t (&w)[64], const uint32_t (&bv)[16]) {
#pragma unroll
    for (int i = 0; i < 16; i++) c[i >> 2][i & 3] = 0.f;
#pragma unroll
    for (int j = 0; j < 4; j++)
#pragma unroll
        for (int i = 0; i < 4; i++)
            mma16816(c[i], w[16 * j + 4 * i], w[16 * j + 4 * i + 1], w[16 * j + 4 * i + 2], w[16 * j + 4 * i + 3],
                     bv[4 * j + (i & 2)], bv[4 * j + (i & 2) + 1]);
}
__device__ __forceinline__ void gemv_store(const float (&c)[4][4], uint32_t ra, bool hi) {
    sts128f(ra, hi ? c[1][0] + c[3][0] : c[0][0] + c[2][0], hi ? c[1][1] + c[3][1] : c[0][1] + c[2][1],
            hi ? c[1][2] + c[3][2] : c[0][2] + c[2][2], hi ? c[1][3] + c[3][3] : c[0][3] + c[2][3]);
}
__device__ __forceinline__ void gemv_store2(const float (&c)[4][4], uint32_t ra, bool hi) {
    float r[4];
#pragma unroll
    for (int i = 0; i < 4; i++) {
        float a = hi ? c[0][i] : c[1][i], b = hi ? c[2][i] : c[3][i];
        asm volatile("add.f32 %0, %1, %2;" : "=f"(r[i]) : "f"(a), "f"(b));
    }
    sts128f(ra, r[0], r[1], r[2], r[3]);
}

enum { MAP_MOD, MAP_WQ, MAP_K, MAP_V, MAP_WO, MAP_W1, MAP_W2, MAP_GB };
struct Params {
    const __nv_bfloat16 *wmod, *x, *b1, *b2, *c;
    __nv_bfloat16* out;
    CUtensorMap map[8];
};

__global__ void __launch_bounds__(NTHR, 1) adaln_decode_kernel(const __grid_constant__ Params p) {
    extern __shared__ __align__(1024) unsigned char smem[];
    const uint32_t sb = (uint32_t)__cvta_generic_to_shared(smem);
    const int cta = blockIdx.x;
    const bool leader = elect_one();
    if (threadIdx.x < 32) {
        if (leader) {
            const uint32_t skip = cta >= N_MOD_CTA, fb = sb + SM_FULL + skip * 40;
#pragma unroll
            for (int i = 0; i < 5; i++) mbar_init(fb + 8 * i, 1);
            asm volatile("fence.mbarrier_init.release.cluster;" ::: "memory");
#pragma unroll 1
            for (int i = 0; i < 5; i++) {
                mbar_expect(fb + 8 * i, TILE_BYTES);
                tma2d(sb + SM_RING + (skip * 5 + i) * TILE_BYTES, &p.map[MAP_MOD + skip], cta * 32, i * 128, fb + 8 * i);
            }
#pragma unroll
            for (int i = 0; i < 5; i++) mbar_init(sb + SM_FULL + (skip ^ 1) * 40 + 8 * i, 1);
            asm volatile("fence.mbarrier_init.release.cluster;" ::: "memory");
            if (skip) {
#pragma unroll
                for (int i = 0; i < 5; i++) mbar_arrive(sb + SM_FULL + 8 * i);
            }
        }
        bar_sync(BAR_INIT, 13 * 32);
        bar_arrive(BAR_INIT2, (NGW + 1) * 32);
    } else if (threadIdx.x < 13 * 32) {
        if (leader) {
            const uint32_t w = threadIdx.x >> 5, a = sb + SM_FULL + w * 32 + 48;
#pragma unroll
            for (int i = 0; i < 2; i++) {
                mbar_init(a + i * 8, w < 5 ? 1 : w < 11 ? 2 : 5);
                mbar_init(a + 16 + i * 8, w < 4 ? 1 : w < 10 ? 2 : 5);
            }
            asm volatile("fence.mbarrier_init.release.cluster;" ::: "memory");
        }
        bar_arrive(BAR_INIT, 13 * 32);
    } else if (leader) {
        if (threadIdx.x & 32) {
#pragma unroll
            for (int i = 0; i < NPF; i++)
                asm volatile("cp.async.bulk.prefetch.L2.global [%0], %1;" ::"l"(p.wmod + (size_t)(cta + i * 128) * 6 * DM), "n"(N_MOD_CTA * 64) : "memory");
        } else asm volatile("prefetch.tensormap [%0];" ::"l"(&p.map[cta < N_MOD_CTA ? MAP_MOD : MAP_WQ]) : "memory");
    }
    __syncwarp();
    if (threadIdx.x < 32) {
        if (!elect_one()) asm volatile("exit;");
        const uint32_t fullb = sb + SM_FULL;
        const int sg0 = cta < N_MOD_CTA ? 1 : 2;
        uint32_t f = 40 * sg0;
        uint32_t w = f - 8 * W_PRO, wpar = 0;
#pragma unroll 1
        for (int sg = sg0; sg < NSEG; sg++) {
            const int kv = ((cta & 3) * NH + (cta >> 2)) * SK + (SK - WIN);
            uint4 s0 = make_uint4(sg, sg == 2 ? 0 : cta * 32, sg == 2 ? kv : 0, sg == 2 ? TILE_KEYS : 128);
            uint4 s1 = make_uint4(sg == 2 ? kv + (MID_LO - IT_K) * TILE_KEYS : DM, TILE_BYTES, 0, 0);
            uint32_t wbase = fullb;
            if (sg > 2) {
                if (sg == 3) { mbar_wait(sb + SM_BSEG, 0); w = 8 * ((MID_LO + 1) % NSLOT); wpar = MID_LO + 1 < NSLOT; }
                s0 = lds128(sb + SM_SEG + sg * 32); s1 = lds128(sb + SM_SEG + sg * 32 + 16);
                wbase += 8 * NSLOT;
            }
            const CUtensorMap* map = &p.map[s0.x];
            const int c0 = s0.y, dc1 = s0.w, c1_end = s1.x, bytes = s1.y, dpos = s1.w;
            int c1 = s0.z, pos = s1.z;
            uint32_t ring = sb + SM_RING;
#pragma unroll 1
            while (c1 != c1_end) {
                const uint32_t due = lds32v(sb + SM_TREF) + pos;
                mbar_wait(wbase + w, wpar);
                mbar_expect(fullb + f, bytes);
                if (dpos) while ((unsigned)(due - sm_clock() - 1) < 20000u) { }
                tma2d(ring + f * (TILE_BYTES / 8), map, c0, c1, fullb + f);
                c1 += dc1; pos += dpos; ring += bytes - TILE_BYTES;
                f += 8; if (f == 8 * NSLOT) f = 0;
                w += 8; if (w == 8 * NSLOT) { w = 0; wpar ^= 1; }
            }
            if (sg == 5) { mbar_arrive(sb + SM_BTRIG); }
            if (sg == 6) {
                mbar_wait(wbase + w, wpar);
                f += 8; if (f == 8 * NSLOT) f = 0;
                w += 8; if (w == 8 * NSLOT) { w = 0; wpar ^= 1; }
            }
        }
        asm volatile("exit;");
    }
    const int warp = __shfl_sync(0xffffffffu, (threadIdx.x >> 5) - 1, 0);
    const int lane = threadIdx.x & 31;
    const int g = lane >> 2, t = lane & 3;
    const int head = cta >> 2, sub = cta & 3;
    const int rj = cta & 15;
    const bool is_w2 = rj % 3 == 0 && rj < 15;
    const int role = is_w2 ? (cta >> 4) * 5 + rj / 3 : (rj - (rj + 2) / 3) * 8 + (cta >> 4);
    const bool is_w1 = !is_w2 && role < N_W1_CTA;
    const bool is_gb = !is_w2 && !is_w1 && role < N_W1_CTA + 20;
    Scratch* const S = &g_s;

    if (warp < NGW) {
        if (warp == 7) {
            if (lane >= 3 && lane < NSEG) {
                const int kv = (sub * NH + head) * SK + (SK - WIN);
                const int first = lane == 3 ? MID_LO : lane == 4 ? IT_V : MID_HI;
                int cnt = lane == 3 ? IT_V - MID_LO : lane == 4 ? MID_HI - IT_V : IT_WO - MID_HI;
                int map = lane == 3 ? MAP_K : MAP_V, c0 = 0, c1 = kv + (first - (lane == 3 ? IT_K : IT_V)) * TILE_KEYS, dc1 = TILE_KEYS;
                int pos = first * 32, dpos = 32;
                const int pos_ve = MID_HI * 32 + VE_D, pos_wo = pos_ve + (IT_WO - 1 - MID_HI) * VE_S + WO_D;
                if (lane == 5) { pos = pos_ve; dpos = VE_S; }
                if (lane == 6) { map = MAP_WO; c0 = (cta & 7) * 80; c1 = (cta >> 3) * 2 * DH; dc1 = 64; cnt = 4; pos = pos_wo; dpos = WO_S; }
                if (lane == 7) {
                    map = is_w1 ? MAP_W1 : is_w2 ? MAP_W2 : MAP_GB;
                    c0 = is_w2 ? role * 16 : is_w1 ? role * 32 : (role - N_W1_CTA + 100) * 32;
                    c1 = 0; dc1 = is_w2 ? 256 : 128; cnt = is_w2 ? 7 : is_w1 || is_gb ? 5 : 0;
                    pos = pos_wo + 3 * WO_S + (is_w1 ? F1_D : is_w2 ? F2_D : F3_D); dpos = is_w1 ? F1_S : is_w2 ? F2_S : F3_S;
                }
                const uint32_t a = sb + SM_SEG + lane * 32;
                sts64(a, map, c0); sts64(a + 8, c1, dc1);
                sts64(a + 16, c1 + cnt * dc1, lane == 6 ? WO_BYTES : TILE_BYTES);
                sts64(a + 24, (pos - W_MID) * CLK32 + (((cta * 45) & 127) - 64) * PHASE * CLK32 / 128, dpos * CLK32);
            }
            __syncwarp();
        }
        if (warp == 0 && lane == 0) sts32(sb + SM_TREF + 4, 0x3f803f80u);
        bar_sync(BAR_INIT2, (NGW + 1) * 32);
        if (warp == 6) {
            if (elect_one()) {
#pragma unroll
                for (int i = MAP_WQ; i <= MAP_GB; i++) asm volatile("prefetch.tensormap [%0];" ::"l"(&p.map[i]) : "memory");
            }
            uint32_t* pw = &S->probe[0][cta * 8];
            stx32(pw + (lane >> 3) * HALF + (lane & 7), 0);
            stx32(pw + ((lane >> 3) + 4) * HALF + (lane & 7), 0);
            __syncwarp();
            uint32_t best0 = NONE, best1 = NONE;
#pragma unroll 1
            for (int i = 0; i < 2 * NPROBE_MAX; i++) {
                const uint32_t t0 = sm_clock();
                uint32_t v = 0;
                asm volatile("{\n.reg .pred p;\nsetp.eq.u32 p, %2, 0;\n@p atom.relaxed.gpu.global.inc.u32 %0, [%1], 0x7fffffff;\n}"
                             : "+r"(v) : "l"(near_copy(pw + (i & 6) * HALF, i & 1)), "r"(lane) : "memory");
                const uint32_t dt = sm_clock_after(v) - t0;
                if (i & 1) best1 = min(best1, dt); else best0 = min(best0, dt);
                const uint32_t lo = min(best0, best1), hi = max(best0, best1);
                if (__any_sync(0xffffffffu, i >= 2 * NPROBE - 1 && lo < 390 && hi > lo + 90)) break;
            }
            asm volatile("{\n.reg .pred q;\n.reg .u32 n, m;\nmov.u32 n, 0;\nLOOP:\n.pragma \"nounroll\";\n"
                         "ld.acquire.gpu.global.u32 m, [%0];\nsetp.lt.u32 q, m, %1;\n" POLL_TAIL("nanosleep.u32 1000;\n")
                         ::"l"(&S->init_cnt), "n"(NCTA) : "memory");
            if (lane == 0) {
                sts32(sb + SM_TREF + 8, best1 < best0);
                mbar_arrive(sb + SM_BML);
                mbar_arrive_n(sb + SM_BTRIG, 2);
            }
        }
        if (warp == 8) {
#pragma unroll 1
            for (int n = 0; n < CNT_HI; n++) {
                mbar_wait(sb + SM_FULL + 8 * (n % NSLOT), (n / NSLOT) & 1);
                asm volatile("{\n.reg .pred p;\nsetp.eq.u32 p, %1, 0;\n@p red.relaxed.gpu.global.inc.u32 [%0], 0x7fffffff;\n}"
                             ::"l"(&S->prog), "r"(((n - cta) & 3) | lane | (n < CNT_LO)) : "memory");
                __syncwarp();
                if (lane == 0) mbar_arrive(sb + SM_EMPTY + 8 * (n % NSLOT));
            }
            if (ldx32(&S->prog) != NONE && lane == 0) mbar_arrive(sb + SM_BTRIG);
        }
        if (warp == 7) {
            mbar_wait_sleep<200>(sb + SM_FULL + 8 * (CNT_LO + 4));
#pragma unroll 1
            for (unsigned n = 0; n < SPIN_MAX; n++) {
                const uint32_t t0 = sm_clock();
                const uint32_t total = ldx32(&S->prog);
                if (lane == 0) {
                    sts32(sb + SM_TREF, t0 - (total + CNT_LO * 32) * CLK32);
                    if (n == 0) mbar_arrive_n(sb + SM_BSEG, 5);
                }
                if (__any_sync(0xffffffffu, total >= (CNT_HI - CNT_LO - 3) * 32)) break;
                __nanosleep(SMP_NS);
            }
            if (lane == 0) mbar_arrive(sb + SM_BTRIG);
        }
        if (warp == 5) {
            __nanosleep(INIT_NS);
            const int hf = (lane >> 4) * HALF, l = lane & 15;
            stx128(o_at(cta >> 3, sub) + (head & 1) * 64 + l * 4 + hf, NONE);
            if (lane < 10) stx128(&S->acc[0][0] + cta * 10 + lane, 0);
            if (l < 10) stx32(x2_at(sub, head * 10 + l) + hf, NONE);
            if (is_w1) stx128(h1_at(role) + l * 4 + hf, NONE);
            if (is_gb) stx128(gb_at(l >> 2) + (role - N_W1_CTA) * 16 + t * 4 + hf, NONE);
            __syncwarp();
            if (lane == 0) asm volatile("red.release.gpu.global.add.u32 [%0], 1;" ::"l"(&S->init_cnt) : "memory");
        }
        __syncwarp();
        const int lr = (lane & 7) + (lane >> 4) * 8, lc = (lane >> 3) & 1;
        const uint32_t aoff32 = lr * 64 + ((lc ^ ((lr >> 1) & 3)) << 4);
        const bool hi = t >= 2, ff = is_w1 || is_w2 || is_gb;
        if (warp < 5) {
            uint32_t w[64], bv[16];
#pragma unroll 1
            for (int op = 0; op < 3; op++) {
                const int slot = (op ? IT_WQ : IT_MOD) + warp;
                if (op < 2) {
                    mbar_wait(sb + SM_FULL + 8 * slot, 0);
                    load_a(w, sb + SM_RING + slot * TILE_BYTES + aoff32, false);
                    bar_sync(BAR_ACT, N_AG5);
                }
                const uint32_t ba = sb + (lane >> 3) * 16 + warp * 256 + (op == 1 ? SM_PRE + (lane & 7) * ACT_LD : SM_ACT + (lane & 3) * ACT_LD);
#pragma unroll
                for (int j = 0; j < 4; j++) ldsm4(&bv[4 * j], ba + j * 64);
                float c[4][4];
                gemv_mma(c, w, bv);
                gemv_store(c, sb + lane * 16 + warp * 512 + (op == 1 ? SM_RED1 : SM_RED), hi);
                if (op == 1) gemv_store2(c, sb + lane * 16 + warp * 512 + SM_RED2, hi);
                __syncwarp();
                if (op == 1) {
                    if (lane == 0) mbar_arrive(sb + SM_BPRE);
                } else {
                    if (op == 0 || !(warp & 2)) bar_arrive(BAR_RED, N_AG5);
                    if (lane == 0) mbar_arrive(sb + SM_EMPTY + 8 * slot);
                }
            }
            const int pb = (t & 1) * 2 + (g & 1), pr = (cta & 7) * 40 + warp * 8 + (t >> 1) * 4 + (g >> 1);
            float x0 = 0.f, x1 = 0.f;
            uint32_t gw = 0;
            const uint32_t *xfar = nullptr, *xnear = nullptr;
            const uint32_t full = sb + SM_FULL + 8 * (IT_WO % NSLOT);
            const uint32_t aa = sb + SM_RING + (IT_WO % NSLOT) * TILE_BYTES + lr * 160 + warp * 32 + lc * 16;
            const uint32_t ba = sb + SM_OACT + (lane & 3) * OACT_LD + (lane >> 3) * 16;
#pragma unroll 1
            for (int rd = 0; rd < 3; rd++) {
                const bool real = rd == 2;
                if (rd) {
                    if (real) {
                        const uint32_t xw = ldx32(p.x + pb * DM + pr * 2);
                        const float pv = lds32f(sb + SM_PIV + pb * 4);
                        x0 = blo(xw) - pv; x1 = bhi(xw) - pv;
                        gw = ~poll32<64>(&S->mod[pb][2 * 320 + pr], 0);
                        mbar_wait_sleep<300>(sb + SM_BTRIG);
                        const uint32_t side = lds32v(sb + SM_TREF + 8);
                        xfar = near_copy(x2_at(pb, pr), side ^ 1);
                        xnear = near_copy(x2_at(pb, pr), side);
                    }
                    uint32_t w[64], bv[16];
#pragma unroll
                    for (int j = 0; j < 2; j++) {
                        if (real) mbar_wait(full + j * 8, (IT_WO / NSLOT) & 1);
#pragma unroll
                        for (int i = 0; i < 4; i++) ldsm4t(&w[16 * j + 4 * i], aa + j * WO_BYTES + i * 2560);
                    }
                    if (real) bar_sync(BAR_ACT, N_AG5);
                    uint32_t b2[16];
#pragma unroll
                    for (int j = 0; j < 4; j++) { ldsm4(&bv[4 * j], ba + j * 64); ldsm4(&b2[4 * j], ba + 256 + j * 64); }
                    float c[4][4] = {};
#pragma unroll
                    for (int j = 0; j < 4; j++) {
                        if (j >= 2) {
                            if (real) mbar_wait(full + j * 8, (IT_WO / NSLOT) & 1);
#pragma unroll
                            for (int i = 0; i < 4; i++) ldsm4t(&w[16 * j + 4 * i], aa + j * WO_BYTES + i * 2560);
                        }
                        const uint32_t* a = &w[16 * j];
                        const uint32_t* b = j < 2 ? &bv[8 * j] : &b2[8 * (j - 2)];
#pragma unroll
                        for (int i = 0; i < 4; i++) mma16816(c[i], a[4 * i], a[4 * i + 1], a[4 * i + 2], a[4 * i + 3], b[2 * i], b[2 * i + 1]);
                    }
                    if (real) {
                        const float u0 = hi ? (c[0][2] + c[1][2]) + (c[2][2] + c[3][2]) : (c[0][0] + c[1][0]) + (c[2][0] + c[3][0]);
                        const float u1 = hi ? (c[0][3] + c[1][3]) + (c[2][3] + c[3][3]) : (c[0][1] + c[1][1]) + (c[2][1] + c[3][1]);
                        const float sx = __shfl_xor_sync(0xffffffffu, (g & 1) ? u0 : u1, 4);
                        const float y0 = (g & 1) ? sx : u0, y1 = (g & 1) ? u1 : sx;
                        const float4 o = atom128(&S->acc[(cta & 7) * 5 + warp][lane], y0, y1, 1.f);
                        const uint32_t x2w = pack2(fmaf(blo(gw), o.x, fmaf(blo(gw), y0, x0)), fmaf(bhi(gw), o.y, fmaf(bhi(gw), y1, x1)));
                        if (o.z == (float)(NH / 2 - 1)) {
                            publish(xfar, x2w);
                            publish(xnear, x2w);
                        }
                        __syncwarp();
                        if (warp == 0 && lane == 0) mbar_arrive_n(sb + SM_BATOM, 5);
                    }
                }
                if ((warp & 2) && (rd == 0 || (real && ff && !is_w2))) {
                    if (!real || is_w1) {
                        mbar_wait(sb + SM_BPRE, rd >> 1);
                        const uint32_t i8 = ((warp & 1) * 32 + lane) * 8;
                        float2 pa = lds64f(sb + SM_RED1 + i8), pc = lds64f(sb + SM_RED2 + (i8 ^ 32));
#pragma unroll
                        for (int j = 1; j < 5; j++) {
                            const float2 u = lds64f(sb + SM_RED1 + i8 + j * 512), v = lds64f(sb + SM_RED2 + (i8 ^ 32) + j * 512);
                            pa.x += u.x; pa.y += u.y; pc.x += v.x; pc.y += v.y;
                        }
                        sts64(sb + SM_RED + 5 * 512 + (i8 & 32) * 16 + i8, __float_as_uint(pa.x), __float_as_uint(pa.y));
                        sts64(sb + SM_RED + 6 * 512 - (i8 & 32) * 16 + i8, __float_as_uint(pc.x), __float_as_uint(pc.y));
                    }
                    if (real) bar_arrive(BAR_RED2, N_AG7); else bar_arrive(BAR_RED, N_AG5);
                }
            }
        }
        if (warp < 5 ? (warp & 2) && is_w2 : ff) {
            const int gw = warp < 5 ? warp + 3 : warp - 5;
            const int item = IT_FF + gw, slot = item % NSLOT;
            const uint32_t aa = sb + SM_RING + slot * TILE_BYTES + (is_w2 ? lr * 32 + ((lc ^ ((lr >> 2) & 1)) << 4) : aoff32);
            const uint32_t* src = h1_at(gw * 8) + (g >> 1) * 32 + t * 8 + (g & 1) * 4;
            const uint32_t ba2 = sb + (lane >> 3) * 16 + gw * 256 + SM_ACT + (lane & 3) * ACT_LD;
            const uint32_t ra2 = sb + lane * 16 + gw * 512 + SM_RED;
            uint32_t ba = ba2, ra = sb + SM_SEG;
            uint32_t w[64] = {}, bv[16];
            const int first = is_w1 ? 1 : 2;
#pragma unroll 1
            for (int rd = warp == 9 ? 0 : first; ; rd = rd ? 2 : first) {
                if (rd <= first) {
                    if (rd) {
                        mbar_wait_sleep<300>(sb + SM_BTRIG);
                        src = near_copy(src, lds32v(sb + SM_TREF + 8));
                        ba = is_w1 ? sb + (lane >> 3) * 16 + gw * 256 + SM_PRE + (lane & 7) * ACT_LD : ba2;
                        ra = is_w1 ? sb + lane * 16 + gw * 512 + SM_RED1 : ra2;
                        mbar_wait(sb + SM_FULL + 8 * slot, (item / NSLOT) & 1);
                    }
                    load_a(w, aa, is_w2);
                }
#pragma unroll
                for (int j = 0; j < 16; j++) bv[j] = (j & 3) == 0 && rd && (j < 12 || gw != 6) ? NONE : 0;
                if (rd == 2 && !is_w2) bar_sync(BAR_ACT2, N_AG5);
                if (is_w2) {
                    poll_h1(bv, src);
                } else {
#pragma unroll
                    for (int j = 0; j < 4; j++) ldsm4(&bv[4 * j], ba + j * 64);
                }
                float c[4][4];
                gemv_mma(c, w, bv);
                gemv_store(c, ra, hi);
                asm volatile("{\n.reg .pred p;\nsetp.eq.u32 p, %0, 2;\n@p bar.arrive %1, %2;\n}" ::"r"(rd), "n"(BAR_RED2), "n"(N_AG7) : "memory");
                if (rd == 2) break;
                if (rd == 1) gemv_store2(c, ra + SM_RED2 - SM_RED1, hi);
                __syncwarp();
                if (rd == 1 && lane == 0) mbar_arrive(sb + SM_BPRE);
                ba = ba2; ra = ra2;
            }
        }
    } else {
        const int aw = warp - NGW;
        uint2 xw[5], xn[5];
#pragma unroll
        for (int i = 0; i < 5; i++) xw[i] = ldx64(p.c + aw * DM + (lane + 32 * i) * 4);
#pragma unroll
        for (int i = 0; i < 5; i++) xn[i] = ldx64(p.x + aw * DM + (lane + 32 * i) * 4);
        uint32_t bias = 0, side = 0;
#pragma unroll 1
        for (int pass = 0; pass < 3; pass++) {
            uint32_t tid;
            asm volatile("mov.u32 %0, %%tid.x;" : "=r"(tid));
            const int lane = tid & 31, g = lane >> 2, t = lane & 3;
            const int at = tid - (NGW + 1) * 32;
            const int rb = ((at >> 2) & 1) * 2 + (at & 1), rc = ((at >> 3) & 1) * 16 + ((at >> 1) & 1) * 8 + (at >> 4);
            const uint32_t act_row = sb + SM_ACT + aw * ACT_LD + lane * 8;
            const int w2col = role * 16 + (rc & 15);
            const bool last = pass == 2, fin = last && is_w2, ln = pass == 1 || (last && is_w1);
            uint32_t* dst = pass == 0 ? &S->mod[aw][cta * 16 + lane] : pass == 1 ? &S->q[aw][cta * 16 + lane]
                          : is_w1 ? h1_at(role) + (rb >> 1) * 32 + aw * 8 + (rb & 1) * 4 + (rc >> 3)
                          : is_w2 ? (uint32_t*)(p.out + rb * DM + w2col) : gb_at(rb) + (role - N_W1_CTA) * 16 + (rc >> 1);
            if (last && !fin) dst += ((at >> 4) & 1) * HALF;
            uint32_t r0a = sb + SM_RED + at * 4;
            uint32_t arow = act_row;
            pin(dst); pin(r0a); pin(arow);
            const float e_b = blo(bias);
            if (fin) {
                float x2v = 0.f, gbv = 0.f;
#pragma unroll 1
                for (int real = 0; real < 2; real++) {
                    if (real) {
                        const uint32_t* xp = near_copy(x2_at(rb, w2col >> 1), side);
                        mbar_wait(sb + SM_BATOM, 0);
                        uint32_t w = poll32<64>(xp, NONE);
                        x2v = ((w2col & 1) ? bhi(w) : blo(w)) + lds32f(sb + SM_PIV + rb * 4);
                        w = poll32<64>(near_copy(gb_at(rb) + (w2col >> 1), side), NONE);
                        gbv = (w2col & 1) ? bhi(w) : blo(w);
                        x2v = fmaf(gbv, e_b, x2v);
                        bar_sync(BAR_RED2, N_AG7);
                    }
                    const float y = ((lds32f(r0a) + lds32f(r0a + 512)) + (lds32f(r0a + 1024) + lds32f(r0a + 1536))) +
                                    ((lds32f(r0a + 2048) + lds32f(r0a + 2560)) + lds32f(r0a + 3072));
                    const float y2 = __shfl_xor_sync(0xffffffffu, y, 8);
                    store_out_if(dst, pack2(fmaf(gbv, y2, fmaf(gbv, y, x2v)), 0.f), real && !(at & 8), real);
                }
                break;
            } else if (ln) {
                float2 sc[5];
#pragma unroll
                for (int i = 0; i < 5; i++) sc[i] = lds64f(arow + SM_PRE - SM_ACT + i * 256);
                if (last) {
                    poll_x2(xw, near_copy(x2_at(aw, lane * 2), side), sb + SM_BATOM, sc, arow);
                    bar_arrive(BAR_ACT2, N_AG5);
                } else {
#pragma unroll
                    for (int i = 0; i < 5; i++)
                        sts64(arow + i * 256, mul2(xw[i].x, __float_as_uint(sc[i].x)), mul2(xw[i].y, __float_as_uint(sc[i].y)));
                    bar_arrive(BAR_ACT, N_AG5);
                }
                const uint32_t ones = lds32v(sb + SM_TREF + 4);
                float c[3][4] = {};
#pragma unroll
                for (int i = 0; i < 5; i++) mma16816(c[i % 3], xw[i].x, ones, xw[i].y, ones, xw[i].x, xw[i].y);
                float sq = (g & 1) ? (c[0][1] + c[1][1]) + c[2][1] : (c[0][0] + c[1][0]) + c[2][0];
                float sm = ((c[0][2] + c[1][2]) + c[2][2]) + ((c[0][3] + c[1][3]) + c[2][3]);
                sq += __shfl_xor_sync(0xffffffffu, sq, 4);
                sm += __shfl_xor_sync(0xffffffffu, sm, 1);
                sq += __shfl_xor_sync(0xffffffffu, sq, 9);
                sm += __shfl_xor_sync(0xffffffffu, sm, 2);
                sq += __shfl_xor_sync(0xffffffffu, sq, 18);
                const float mean = sm * (1.f / DM);
                float rstd;
                asm("rsqrt.approx.ftz.f32 %0, %1;" : "=f"(rstd) : "f"(fmaxf(fmaf(sq, 1.f / DM, -mean * mean), 0.f) + 1e-5f));
                if (lane == 0) sts64(sb + SM_ST + aw * 8, __float_as_uint(rstd), __float_as_uint(-mean * rstd));
            } else {
#pragma unroll
                for (int i = 0; i < 5; i++) {
                    const float a = blo(xw[i].x), b = bhi(xw[i].x), c = blo(xw[i].y), d = bhi(xw[i].y);
                    sts64(arow + i * 256, pack2(mul_sigmoid2(a, a * LOG2E), mul_sigmoid2(b, b * LOG2E)),
                          pack2(mul_sigmoid2(c, c * LOG2E), mul_sigmoid2(d, d * LOG2E)));
                }
                if (last) bar_arrive(BAR_ACT2, N_AG5); else bar_arrive(BAR_ACT, N_AG5);
            }
            if (last) bar_sync(BAR_RED2, N_AG7); else bar_sync(BAR_RED, N_AG5);
            {
                const float2 st = lds64f(sb + SM_ST + rb * 8);
                const float u0 = sum5(r0a), u1 = lds32f(r0a + 5 * 512), u2 = lds32f(r0a + 6 * 512);
                const float u = ln ? fmaf(st.x, u0, fmaf(st.y, u1, u2 + e_b)) : u0;
                constexpr float K1 = 2.f * 0.7978845608028654f * LOG2E;
                const float ge = mul_sigmoid2(u, u * fmaf(u * u, K1 * 0.044715f, K1));
                const float r = (last && is_w1) ? ge : u;
                const float o = __shfl_xor_sync(0xffffffffu, r, 16);
                const uint32_t wv = (at & 16) ? pack2(o, r) : pack2(r, o);
                if (last) publish(dst, wv);
                else {
                    if (!(at & 16)) sts32(sb + SM_OACT + (rb * 16 + (rc >> 1)) * 4, ~wv);
                    bar_sync(BAR_A, NAW * 32);
                    if (lane < 16 && (pass != 0 || cta < N_MOD_CTA))
                        stx32(dst, lds32v(sb + SM_OACT + (aw * 16 + lane) * 4));
                }
            }
            const uint32_t t_pub = sm_clock();
            if (pass == 0) {
                float c[4] = {};
#pragma unroll
                for (int i = 0; i < 5; i++) mma16816(c, 0x3f803f80u, 0x3f803f80u, 0x3f803f80u, 0x3f803f80u, xn[i].x, xn[i].y);
                float sm = c[0] + c[1];
                sm += __shfl_xor_sync(0xffffffffu, sm, 1);
                sm += __shfl_xor_sync(0xffffffffu, sm, 2);
                const uint32_t pivot = pack2(sm * (1.f / DM), sm * (1.f / DM));
                if (lane == 0) sts32f(sb + SM_PIV + aw * 4, blo(pivot));
#pragma unroll
                for (int i = 0; i < 5; i++) { xw[i].x = add2(xn[i].x, pivot ^ 0x80008000u); xw[i].y = add2(xn[i].y, pivot ^ 0x80008000u); }
                pause_until(t_pub + MOD_CLK);
                uint2 mr[10] = {};
                poll_shift_scale(mr, &S->mod[aw][lane * 2], act_row + SM_PRE - SM_ACT);
            } else if (pass == 1) {
                pause_until(t_pub + Q_CLK);
                uint32_t qf[16] = {};
                const uint32_t* qsrc = &S->q[sub][head * 64 + t * 4];
                poll_q(qf, qsrc + (g & 1) * 16, qsrc + ((g & 1) ^ 1) * 16);
#pragma unroll
                for (int j = 0; j < 16; j++) qf[j] = ~qf[j];

                int slot = IT_K + aw;
                uint32_t phase = 0;
                float mx = -INFINITY;
                const uint32_t sc_addr = sb + SM_SCORE + (aw * 512 + t * 8 + g) * 4;
                const uint32_t koff0 = g * 256 + (((g & 1) * 4 + t) * 16), koff1 = koff0 ^ 64;
#pragma unroll 1
                for (int i = 0; i < KT; i++) {
                    mbar_wait(sb + SM_FULL + 8 * slot, phase);
                    const uint32_t tile = sb + SM_RING + slot * TILE_BYTES;
                    float s[2][2];
#pragma unroll
                    for (int gr = 0; gr < 2; gr++) {
                        float c0[4] = {0.f, 0.f, 0.f, 0.f}, c1[4] = {0.f, 0.f, 0.f, 0.f};
#pragma unroll
                        for (int j = 0; j < 4; j++) {
                            const uint32_t a = tile + gr * 4096 + ((j & 1) ? koff1 : koff0) + (j >> 1) * 128;
                            const uint4 r0 = lds128(a), r1 = lds128(a + 2048);
                            mma16816(c0, r0.x, r1.x, r0.y, r1.y, qf[4 * j], qf[4 * j + 1]);
                            mma16816(c1, r0.z, r1.z, r0.w, r1.w, qf[4 * j + 2], qf[4 * j + 3]);
                        }
                        s[gr][0] = (g & 1) ? c0[1] + c1[1] : c0[0] + c1[0];
                        s[gr][1] = (g & 1) ? c0[3] + c1[3] : c0[2] + c1[2];
                    }
                    const float sv = (t & 2) ? ((t & 1) ? s[1][1] : s[1][0]) : ((t & 1) ? s[0][1] : s[0][0]);
                    mx = fmaxf(mx, sv);
                    sts32f(sc_addr + i * 128, sv);
                    __syncwarp();
                    if (lane == 0) mbar_arrive(sb + SM_EMPTY + 8 * slot);
                    slot += NAW;
                    if (slot >= NSLOT) { slot -= NSLOT; phase ^= 1; }
                }
                uint2 mr[10];
#pragma unroll
                for (int i = 0; i < 10; i++) {
                    mr[i].x = mr[i].y = 0;
                    ldx64_if(mr[i], &S->mod[aw][3 * 320 + (lane + 32 * i) * 2], is_w1);
                }
                if (is_w1 || is_w2) bias = ldw16(is_w1 ? p.b1 + role * 32 + rc : p.b2 + w2col);
                const float sl2e = 0.08838834764831845f * LOG2E;
#pragma unroll
                for (int o = 1; o < 32; o <<= 1) mx = fmaxf(mx, __shfl_xor_sync(0xffffffffu, mx, o));
                mx *= sl2e;
                {
                    float lsum = 0.f;
                    const uint32_t p_addr = sb + SM_P + (aw * 512 + lane) * 2;
#pragma unroll 4
                    for (int i = 0; i < KT; i++) {
                        const float e = ex2(fmaf(lds32f(sc_addr + i * 128), sl2e, -mx));
                        lsum += e;
                        sts16(p_addr + i * 64, pack2(e, 0.f));
                    }
#pragma unroll
                    for (int o = 1; o < 32; o <<= 1) lsum += __shfl_xor_sync(0xffffffffu, lsum, o);
                    __syncwarp();
                    if (lane == 0) {
                        sts64(sb + SM_ML + aw * 8, __float_as_uint(mx), __float_as_uint(lsum));
                        mbar_arrive(sb + SM_BML);
                    }
                }
                if (is_w1) poll_shift_scale(mr, &S->mod[aw][3 * 320 + lane * 2], act_row + SM_PRE - SM_ACT);
                mbar_wait(sb + SM_BML, 0);
                side = lds32v(sb + SM_TREF + 8);
                float fscale;
                {
                    const uint4 u0 = lds128(sb + SM_ML), u1 = lds128(sb + SM_ML + 16);
                    const float m0 = __uint_as_float(u0.x), m1 = __uint_as_float(u0.z), m2 = __uint_as_float(u1.x), m3 = __uint_as_float(u1.z);
                    const float M = fmaxf(fmaxf(m0, m1), fmaxf(m2, m3));
                    const float L = (__uint_as_float(u0.y) * ex2(m0 - M) + __uint_as_float(u0.w) * ex2(m1 - M)) +
                                    (__uint_as_float(u1.y) * ex2(m2 - M) + __uint_as_float(u1.w) * ex2(m3 - M));
                    fscale = ex2(mx - M) * rcp(L);
                }

                float acc[8][4] = {};
                const bool act = (g >> 1) == t;
                const uint32_t psel_lo = act ? ((g & 1) ? 0x1044u : 0x4410u) : 0x4444u;
                const uint32_t psel_hi = act ? ((g & 1) ? 0x3244u : 0x4432u) : 0x4444u;
                const uint32_t voff = sb + SM_RING + ((lane >> 4) * 8 + (lane & 7)) * 256 + ((lane >> 3) & 1) * 128 + (lane & 7) * 16;
                const uint32_t pv_addr = sb + SM_P + (aw * 512 + g * 4) * 2;
                uint32_t* odst = o_at(cta >> 3, sub) + (head & 1) * 64 + (at >> 1) + (at & 1) * HALF;
                const uint32_t* osrc = near_copy(o_at(cta >> 3, aw) + lane * 4, side);
#pragma unroll 1
                for (int i = 0; i < KT; i++) {
                    const float2 pw = lds64f(pv_addr + i * 64);
                    const uint32_t tile = voff + slot * TILE_BYTES;
                    const uint32_t b0 = __byte_perm(__float_as_uint(pw.x), 0, psel_lo), b1 = __byte_perm(__float_as_uint(pw.x), 0, psel_hi);
                    const uint32_t b2 = __byte_perm(__float_as_uint(pw.y), 0, psel_lo), b3 = __byte_perm(__float_as_uint(pw.y), 0, psel_hi);
                    mbar_wait(sb + SM_FULL + 8 * slot, phase);
                    uint32_t a[8][4];
#pragma unroll
                    for (int c = 0; c < 8; c++) ldsm4t(a[c], tile ^ (c << 4));
#pragma unroll
                    for (int c = 0; c < 8; c++) {
                        mma16816(acc[c], a[c][0], a[c][1], a[c][2], a[c][3], b0, b1);
                        ldsm4t(a[c], (tile ^ (c << 4)) + 4096);
                    }
#pragma unroll
                    for (int c = 0; c < 8; c++) mma16816(acc[c], a[c][0], a[c][1], a[c][2], a[c][3], b2, b3);
                    __syncwarp();
                    if (lane == 0) mbar_arrive(sb + SM_EMPTY + 8 * slot);
                    slot += NAW;
                    if (slot >= NSLOT) { slot -= NSLOT; phase ^= 1; }
                }
                float k1[2][2];
#pragma unroll
                for (int h = 0; h < 2; h++) {
                    float k0[8];
#pragma unroll
                    for (int c = 0; c < 8; c++) k0[c] = acc[c][2 * h] + acc[c ^ 1][2 * h + 1];
#pragma unroll
                    for (int c = 0; c < 8; c++) if (!(c & 2)) k0[c] += __shfl_xor_sync(0xffffffffu, k0[c ^ 2], 1);
#pragma unroll
                    for (int c = 0; c < 2; c++) k1[h][c] = (k0[c] + __shfl_xor_sync(0xffffffffu, k0[c ^ 4], 2)) * fscale;
                }
#pragma unroll
                for (int i = 0; i < 4; i++) sts32f(sb + SM_ORED + (aw * 128 + t * 16 + g) * 4 + (i >> 1) * 256 + (i & 1) * 32, k1[i >> 1][i & 1]);
                bar_sync(BAR_A, NAW * 32);
                const uint32_t oa = sb + SM_ORED + at * 4;
                const float o = (lds32f(oa) + lds32f(oa + 512)) + (lds32f(oa + 1024) + lds32f(oa + 1536));
                const float o2 = __shfl_xor_sync(0xffffffffu, o, 1);
                publish(odst, (at & 1) ? pack2(o2, o) : pack2(o, o2));
                {
                    const uint4 r = poll128(osrc);
                    sts128f(sb + SM_OACT + aw * OACT_LD + lane * 16, __uint_as_float(r.x), __uint_as_float(r.y), __uint_as_float(r.z), __uint_as_float(r.w));
                }
                bar_arrive(BAR_ACT, N_AG5);
                if (!is_w1 && !is_w2 && !is_gb) break;
#pragma unroll
                for (int i = 0; i < 5; i++) {
                    xw[i].x = xw[i].y = 0;
                    ldx64_if(xw[i], p.c + aw * DM + (lane + 32 * i) * 4, is_gb);
                }
#pragma unroll
                for (int i = 0; i < 5; i++) xn[i].x = xn[i].y = 0;
            }
        }
        if (!is_w1 && !is_w2) {
            poll32<200>(near_copy(x2_at(aw, g * 40 + t), side), NONE);
            const int i = (role - N_W1_CTA) * 128 + aw * 32 + lane;
            if (i < (4 * 1920 + 4 * 2048) / 4) stx128(&S->mod[0][0] + i * 4, 0);
            if (i == 0) { stx32(&S->init_cnt, 0); stx32(&S->prog, 0); }
        }
    }
}

typedef CUresult (*EncodeFn)(CUtensorMap*, CUtensorMapDataType, cuuint32_t, void*, const cuuint64_t*, const cuuint64_t*,
                             const cuuint32_t*, const cuuint32_t*, CUtensorMapInterleave, CUtensorMapSwizzle,
                             CUtensorMapL2promotion, CUtensorMapFloatOOBfill);

void make_map(EncodeFn enc, CUtensorMap* m, void* ptr, int rows, int cols, int box_rows, int box_cols, int promo) {
    const cuuint64_t dims[2] = {(cuuint64_t)cols, (cuuint64_t)rows};
    const cuuint64_t strides[1] = {(cuuint64_t)cols * 2};
    const cuuint32_t box[2] = {(cuuint32_t)box_cols, (cuuint32_t)box_rows};
    const cuuint32_t es[2] = {1, 1};
    enc(m, CU_TENSOR_MAP_DATA_TYPE_BFLOAT16, 2, ptr, dims, strides, box, es, CU_TENSOR_MAP_INTERLEAVE_NONE,
        box_cols == 32 ? CU_TENSOR_MAP_SWIZZLE_64B : box_cols == 16 ? CU_TENSOR_MAP_SWIZZLE_32B : CU_TENSOR_MAP_SWIZZLE_NONE,
        (CUtensorMapL2promotion)promo, CU_TENSOR_MAP_FLOAT_OOB_FILL_NONE);
}

}

#define PROMO(i) ((i) < 2 ? CU_TENSOR_MAP_L2_PROMOTION_L2_128B : CU_TENSOR_MAP_L2_PROMOTION_NONE)
extern "C" void kernel_launch(void* const* d_in, const int* in_sizes, int n_in, void* d_out, int out_size) {
    (void)in_sizes; (void)n_in; (void)out_size;
    void* fn = nullptr;
    cudaDriverEntryPointQueryResult qr;
    cudaGetDriverEntryPoint("cuTensorMapEncodeTiled", &fn, cudaEnableDefault, &qr);
    EncodeFn enc = (EncodeFn)fn;
    Params p;
    make_map(enc, &p.map[MAP_MOD], d_in[11], DM, 6 * DM, 128, 32, PROMO(0));
    make_map(enc, &p.map[MAP_GB], d_in[11], DM, 6 * DM, 128, 32, PROMO(6));
    make_map(enc, &p.map[MAP_WQ], d_in[3], DM, NH * DH, 128, 32, PROMO(1));
    make_map(enc, &p.map[MAP_K], d_in[1], 4 * NH * SK, DH, TILE_KEYS, DH, PROMO(2));
    make_map(enc, &p.map[MAP_V], d_in[2], 4 * NH * SK, DH, TILE_KEYS, DH, PROMO(2));
    make_map(enc, &p.map[MAP_WO], d_in[4], NH * DH, DM, 64, 80, PROMO(3));
    make_map(enc, &p.map[MAP_W1], d_in[6], DM, FF, 128, 32, PROMO(4));
    make_map(enc, &p.map[MAP_W2], d_in[8], FF, DM, 256, 16, PROMO(5));
    p.x = (const __nv_bfloat16*)d_in[0];
    p.wmod = (const __nv_bfloat16*)d_in[11];
    p.b1 = (const __nv_bfloat16*)d_in[7];
    p.b2 = (const __nv_bfloat16*)d_in[9];
    p.c = (const __nv_bfloat16*)d_in[10];
    p.out = (__nv_bfloat16*)d_out;
    cudaFuncSetAttribute(adaln_decode_kernel, cudaFuncAttributeMaxDynamicSharedMemorySize, SM_TOTAL);
    adaln_decode_kernel<<<NCTA, NTHR, SM_TOTAL>>>(p);
}
```
